```python
import torch

def _softmax(x, axis=-1):
    return torch.softmax(x, dim=axis)

def _gelu(x):
    return torch.nn.functional.gelu(x, approximate='tanh')

def _silu(x):
    return torch.nn.functional.silu(x)

def _sigmoid(x):
    return torch.sigmoid(x)

def _layernorm(x, axis=-1, eps=1e-05):
    m = x.mean(dim=axis, keepdim=True)
    v = x.var(dim=axis, keepdim=True, unbiased=False)
    return (x - m) / torch.sqrt(v + eps)

def _scatter_add(tgt, idx, src, axis=0):
    return tgt.clone().index_add_(axis, idx, src)

def _segment_sum(src, seg, n):
    out = torch.zeros((n,) + src.shape[1:], dtype=src.dtype)
    return out.index_add_(0, seg, src)

def _pad(x, pw):
    flat = tuple((v for pair in reversed(pw) for v in pair))
    return torch.nn.functional.pad(x, flat)
kernel_name = 'sequential_preLN__linear_kernel_hedgehog__mixer_gmlp__prompt'

def setup_inputs():

    _w = lambda a: (lambda t: t.to(torch.bfloat16) if t.is_floating_point() else t)(torch.as_tensor(a))

    def _A_setup():
        B, S, D, H = (1, 2048, 512, 32)
        Dh = D // H
        return {'x': _w((lambda *s: torch.randn(*s, dtype=torch.bfloat16) * 0.05)(B, S, D)), 'wqkv': _w((lambda *s: torch.randn(*s, dtype=torch.bfloat16) * 0.2)(D, 3 * D)), 'w_phi': _w((lambda *s: torch.randn(*s, dtype=torch.bfloat16) * 0.2)(H, Dh, Dh) * Dh ** (-0.5)), 'wo': _w((lambda *s: torch.randn(*s, dtype=torch.bfloat16) * 0.05)(D, D))}
    _A_in = _A_setup()

    def _B_setup():
        B, S, D, F = (1, 2048, 512, 1376)
        Fh = F // 2
        return {'x': _w((lambda *s: torch.randn(*s, dtype=torch.bfloat16) * 0.05)(B, S, D)), 'w_in': _w((lambda *s: torch.randn(*s, dtype=torch.bfloat16) * 0.2)(D, 2 * Fh)), 'w_sp': _w(0.01 * (lambda *s: torch.randn(*s, dtype=torch.bfloat16) * 0.2)(S, S)), 'b_sp': _w(1.0 + 0.01 * (lambda *s: torch.randn(*s, dtype=torch.bfloat16) * 0.05)(S)), 'w_out': _w((lambda *s: torch.randn(*s, dtype=torch.bfloat16) * 0.05)(Fh, D))}
    _B_in = _B_setup()
    return {'A_x': _A_in['x'], 'A_wqkv': _A_in['wqkv'], 'A_w_phi': _A_in['w_phi'], 'A_wo': _A_in['wo'], 'B_x': _B_in['x'], 'B_w_in': _B_in['w_in'], 'B_w_sp': _B_in['w_sp'], 'B_b_sp': _B_in['b_sp'], 'B_w_out': _B_in['w_out']}

def reference(A_x, A_wqkv, A_w_phi, A_wo, B_x, B_w_in, B_w_sp, B_b_sp, B_w_out):

    def _A_ref(x, wqkv, w_phi, wo):
        B, S, D = x.shape
        H = 32
        Dh = D // H
        qkv = (lambda x, *d: x.permute(*d))((x @ wqkv).reshape(B, S, 3, H, Dh), 2, 0, 3, 1, 4)
        q, k, v = (qkv[0], qkv[1], qkv[2])
        pq = torch.einsum('bhsd,hdf->bhsf', q, w_phi)
        pk = torch.einsum('bhsd,hdf->bhsf', k, w_phi)
        phi_q = torch.concatenate([_softmax(pq, axis=-1), _softmax(-pq, axis=-1)], axis=-1)
        phi_k = torch.concatenate([_softmax(pk, axis=-1), _softmax(-pk, axis=-1)], axis=-1)
        kv = torch.einsum('bhsf,bhsd->bhfd', phi_k, v)
        z = torch.einsum('bhsf->bhf', phi_k)
        num = torch.einsum('bhqf,bhfd->bhqd', phi_q, kv)
        den = torch.einsum('bhqf,bhf->bhq', phi_q, z)[..., None] + 1e-06
        o = num / den
        return (lambda x, *d: x.permute(*d))(o, 0, 2, 1, 3).reshape(B, S, D) @ wo

    def _B_ref(x, w_in, w_sp, b_sp, w_out):
        B, S, D = x.shape
        F = w_in.shape[-1]
        Fh = F // 2
        z = _gelu(torch.einsum('bsd,df->bsf', x, w_in))
        z1 = z[..., :Fh].clone()
        z2 = _layernorm(z[..., Fh:], axis=-1)
        g = torch.einsum('ts,bsf->btf', w_sp, z2) + b_sp[None, :, None]
        return torch.einsum('bsf,fd->bsd', z1 * g, w_out)
    x = A_x
    h = x + _A_ref(_layernorm(x, axis=-1), A_wqkv, A_w_phi, A_wo)
    h2 = h + _B_ref(_layernorm(h, axis=-1), B_w_in, B_w_sp, B_b_sp, B_w_out)
    return h2
```

```cpp
#include <cuda_runtime.h>
#include <cuda_bf16.h>
#include <cuda.h>
#include <stdint.h>

#define PROFILE 0

namespace {

constexpr int NCTA = 128;
constexpr int NTHREADS = 384;

constexpr int SM_A = 0;
constexpr int SM_B = 131072;
constexpr int SM_BAR = 229376;
constexpr int SM_CS1 = SM_BAR + 1024;
constexpr int SM_CS2 = SM_CS1 + 768;
constexpr int SM_ORD = SM_CS2 + 704;
constexpr int SM_XS = SM_CS2;
constexpr int SM_HS = SM_B + 6144;
constexpr int SM_TOTAL = 232448;
constexpr int SM_VS = SM_B;
constexpr int SM_KVP = SM_B + 21504;
constexpr int SM_PHIK = SM_B + 32768;
constexpr int SM_KVS = SM_B;
constexpr int SM_WO = SM_B + 32768;
constexpr int SM_Z2 = SM_B + 8192;
constexpr int U_SLOT = 22528;
constexpr int SM_ZERO = SM_A + 6 * U_SLOT;

enum {
  B_F = 0,
  B_EW = B_F + 12,
  B_P1DONE = B_EW + 6,
  B_EMPTY = B_P1DONE + 1,
  B_FULL = B_EMPTY + 4,
  B_EU = B_FULL + 4,
  B_TWO_END = B_EU + 2,
  B_CS1 = B_TWO_END,
  B_CS2 = B_CS1 + 1,
  B_FWO = B_CS2 + 1,
  B_FO = B_FWO + 2,
  B_FWIN = B_FO + 8,
  B_FH = B_FWIN + 8,
  B_FWOUT = B_FH + 8,
  B_STG = B_FWOUT + 4,
  B_PUB = B_STG + 5,
  B_FX67 = B_PUB + 5,
  B_HS = B_FX67 + 1,
  B_POIS = B_HS + 1,
  B_ISS = B_POIS + 1,
  B_FU = B_ISS + 1,
  B_VAL = B_FU + 7,
  B_RETRY = B_VAL + 7,
  B_FZ = B_RETRY + 2,
  B_RP = B_FZ + 2,
  B_COUNT = B_RP + 1
};
static_assert(B_COUNT * 8 <= 1024, "too many barriers");

__device__ __align__(128) unsigned g_epoch[NCTA * 32];
__device__ int g_err;
__device__ __align__(128) float g_kvacc[8 * 78 * 32];
__device__ __align__(128) unsigned g_cnt_cs1[8 * 32];
__device__ __align__(128) unsigned g_cnt_cs2[8 * 32];
__device__ __align__(128) float g_cs[2][8 * 384];
__device__ __align__(128) uint4 g_winp[8 * 2 * 64 * 11 * 8];
__device__ __align__(128) uint32_t g_obuf[16 * 16 * 2048];
__device__ __align__(128) uint32_t g_hbuf[16 * 16 * 2048];
__device__ __align__(128) uint4 g_xstat[2048];
__device__ __align__(128) uint2 g_hstat[2048 * 8];
__device__ __align__(128) uint2 g_zstat[2048 * 8];
__device__ __align__(128) uint32_t g_z2n[8 * 256 * 11 * 32];
__device__ __align__(128) uint32_t g_ubuf[16 * 86 * 512];
__device__ __align__(128) unsigned g_flag_o[16 * 32];
__device__ __align__(128) unsigned g_flag_h[16 * 32];
__device__ __align__(128) unsigned g_flag_u[16 * 32];
__device__ __align__(128) unsigned g_flag_z[8 * 32];

__device__ __forceinline__ uint32_t smem_u32(const void* p) { return (uint32_t)__cvta_generic_to_shared(p); }
__device__ __forceinline__ void mbar_init(uint32_t bar, int cnt) {
  asm volatile("mbarrier.init.shared::cta.b64 [%0], %1;" ::"r"(bar), "r"(cnt) : "memory");
}
__device__ __forceinline__ void mbar_expect_tx(uint32_t bar, uint32_t bytes) {
  asm volatile("mbarrier.arrive.expect_tx.shared::cta.b64 _, [%0], %1;" ::"r"(bar), "r"(bytes) : "memory");
}
__device__ __forceinline__ void mbar_arrive(uint32_t bar) {
  asm volatile("mbarrier.arrive.shared::cta.b64 _, [%0];" ::"r"(bar) : "memory");
}
__device__ __forceinline__ bool mbar_test(uint32_t bar, uint32_t parity) {
  uint32_t ok;
  asm volatile("{\n.reg .pred p;\nmbarrier.test_wait.parity.shared::cta.b64 p, [%1], %2;\nselp.u32 %0, 1, 0, p;\n}"
               : "=r"(ok) : "r"(bar), "r"(parity) : "memory");
  return ok != 0;
}
__device__ __forceinline__ uint32_t lds32(uint32_t a) {
  uint32_t v;
  asm volatile("ld.shared.b32 %0, [%1];" : "=r"(v) : "r"(a) : "memory");
  return v;
}
__device__ __forceinline__ void mbar_wait(uint32_t bar, uint32_t parity) {
  asm volatile("{\n.reg .pred p;\n.reg .u32 c;\nmov.u32 c, 0;\n"
               "W_%=:\nmbarrier.try_wait.parity.shared::cta.b64 p, [%0], %1;\n@p bra D_%=;\n"
               "add.u32 c, c, 1;\nsetp.lt.u32 p, c, 4194304;\n@p bra W_%=;\ntrap;\nD_%=:\n}"
               ::"r"(bar), "r"(parity) : "memory");
}
__device__ __forceinline__ void bulk_g2s(uint32_t dst, const void* src, uint32_t bytes, uint32_t bar) {
  asm volatile("cp.async.bulk.shared::cluster.global.mbarrier::complete_tx::bytes [%0], [%1], %2, [%3];"
               ::"r"(dst), "l"(src), "r"(bytes), "r"(bar) : "memory");
}
__device__ __forceinline__ void tma2d(uint32_t dst, const CUtensorMap* map, int c0, int c1, uint32_t bar) {
  asm volatile("cp.async.bulk.tensor.2d.shared::cluster.global.mbarrier::complete_tx::bytes [%0], [%1, {%3, %4}], [%2];"
               ::"r"(dst), "l"((uint64_t)map), "r"(bar), "r"(c0), "r"(c1) : "memory");
}
__device__ __forceinline__ void tma3d(uint32_t dst, const CUtensorMap* map, int c0, int c1, int c2, uint32_t bar) {
  asm volatile("cp.async.bulk.tensor.3d.shared::cluster.global.mbarrier::complete_tx::bytes [%0], [%1, {%3, %4, %5}], [%2];"
               ::"r"(dst), "l"((uint64_t)map), "r"(bar), "r"(c0), "r"(c1), "r"(c2) : "memory");
}
__device__ __forceinline__ void prefetch_l2(const void* p, uint32_t bytes) {
  asm volatile("cp.async.bulk.prefetch.L2.global [%0], %1;" ::"l"(p), "r"(bytes) : "memory");
}
__device__ __forceinline__ void prefetch_map(const CUtensorMap* map) {
  asm volatile("prefetch.tensormap [%0];" ::"l"((uint64_t)map) : "memory");
}
__device__ __forceinline__ unsigned ld_rlx(const unsigned* p) {
  unsigned v;
  asm volatile("ld.relaxed.gpu.global.u32 %0, [%1];" : "=r"(v) : "l"(p) : "memory");
  return v;
}
__device__ __forceinline__ void red_rel(unsigned* p, unsigned v) {
  asm volatile("red.release.gpu.global.add.u32 [%0], %1;" ::"l"(p), "r"(v) : "memory");
}
__device__ __forceinline__ void red_v2(float* p, float a, float b) {
  asm volatile("red.relaxed.gpu.global.add.v2.f32 [%0], {%1, %2};" ::"l"(p), "f"(a), "f"(b) : "memory");
}
__device__ __forceinline__ void red_f32(float* p, float a) {
  asm volatile("red.relaxed.gpu.global.add.f32 [%0], %1;" ::"l"(p), "f"(a) : "memory");
}
__device__ __forceinline__ float4 ld_cg4(const float* p) {
  float4 v;
  asm volatile("ld.relaxed.gpu.global.v4.f32 {%0,%1,%2,%3}, [%4];" : "=f"(v.x), "=f"(v.y), "=f"(v.z), "=f"(v.w) : "l"(p) : "memory");
  return v;
}
__device__ __forceinline__ uint4 ld_ll(const uint4* p) {
  unsigned long long a, b;
  asm volatile("ld.relaxed.gpu.global.v2.b64 {%0, %1}, [%2];" : "=l"(a), "=l"(b) : "l"(p) : "memory");
  return make_uint4((unsigned)a, (unsigned)(a >> 32), (unsigned)b, (unsigned)(b >> 32));
}
__device__ __forceinline__ void st_ll(uint4* p, float a, float b, unsigned tag) {
  const unsigned long long w0 = ((unsigned long long)tag << 32) | __float_as_uint(a);
  const unsigned long long w1 = ((unsigned long long)tag << 32) | __float_as_uint(b);
  asm volatile("st.relaxed.gpu.global.v2.b64 [%0], {%1, %2};" ::"l"(p), "l"(w0), "l"(w1) : "memory");
}
__device__ __forceinline__ void st_ll8(uint2* p, float a, float b, unsigned tag) {
  const unsigned long long w0 = ((unsigned long long)((__float_as_uint(b) & 0xFFFFFF00u) | (tag & 0xFFu)) << 32) | __float_as_uint(a);
  asm volatile("st.relaxed.gpu.global.b64 [%0], %1;" ::"l"(p), "l"(w0) : "memory");
}
__device__ __forceinline__ void st_rlx(unsigned* p, unsigned v) {
  asm volatile("st.relaxed.gpu.global.u32 [%0], %1;" ::"l"(p), "r"(v) : "memory");
}
__device__ __forceinline__ void bulk_s2g(void* dst, uint32_t src, uint32_t bytes) {
  asm volatile("cp.async.bulk.global.shared::cta.bulk_group [%0], [%1], %2;" ::"l"(dst), "r"(src), "r"(bytes) : "memory");
}
__device__ __forceinline__ void bulk_red_f32(void* dst, uint32_t src, uint32_t bytes) {
  asm volatile("cp.reduce.async.bulk.global.shared::cta.bulk_group.add.f32 [%0], [%1], %2;" ::"l"(dst), "r"(src), "r"(bytes) : "memory");
}
__device__ __forceinline__ void bulk_commit_wait() {
  asm volatile("cp.async.bulk.commit_group;\ncp.async.bulk.wait_group 0;" ::: "memory");
}
__device__ __forceinline__ void sts64f(uint32_t a, float x, float y) {
  asm volatile("st.shared.v2.f32 [%0], {%1, %2};" ::"r"(a), "f"(x), "f"(y) : "memory");
}
__device__ __forceinline__ void fence_async_global() { asm volatile("fence.proxy.async.global;" ::: "memory"); }
__device__ __forceinline__ void fence_async_smem() { asm volatile("fence.proxy.async.shared::cta;" ::: "memory"); }
__device__ __forceinline__ void bar_sync(int id, int n) { asm volatile("bar.sync %0, %1;" ::"r"(id), "r"(n) : "memory"); }
__device__ __forceinline__ void sts32(uint32_t a, uint32_t v) { asm volatile("st.shared.b32 [%0], %1;" ::"r"(a), "r"(v) : "memory"); }
__device__ __forceinline__ uint4 lds128(uint32_t a) {
  uint4 v;
  asm volatile("ld.shared.v4.b32 {%0,%1,%2,%3}, [%4];" : "=r"(v.x), "=r"(v.y), "=r"(v.z), "=r"(v.w) : "r"(a) : "memory");
  return v;
}
__device__ __forceinline__ float2 lds64f(uint32_t a) {
  float2 v;
  asm volatile("ld.shared.v2.f32 {%0,%1}, [%2];" : "=f"(v.x), "=f"(v.y) : "r"(a) : "memory");
  return v;
}
__device__ __forceinline__ void ldsm4(uint32_t* r, uint32_t a) {
  asm volatile("ldmatrix.sync.aligned.m8n8.x4.shared.b16 {%0,%1,%2,%3}, [%4];"
               : "=r"(r[0]), "=r"(r[1]), "=r"(r[2]), "=r"(r[3]) : "r"(a) : "memory");
}
__device__ __forceinline__ void stsm4(uint32_t a, uint32_t r0, uint32_t r1, uint32_t r2, uint32_t r3) {
  asm volatile("stmatrix.sync.aligned.m8n8.x4.shared.b16 [%0], {%1,%2,%3,%4};" ::"r"(a), "r"(r0), "r"(r1), "r"(r2), "r"(r3) : "memory");
}
__device__ __forceinline__ uint32_t pack2(float lo, float hi) {
  uint32_t r;
  asm("cvt.rn.bf16x2.f32 %0, %1, %2;" : "=r"(r) : "f"(hi), "f"(lo));
  return r;
}
__device__ __forceinline__ float bf_lo(uint32_t w) { return __uint_as_float(w << 16); }
__device__ __forceinline__ float bf_hi(uint32_t w) { return __uint_as_float(w & 0xFFFF0000u); }
__device__ __forceinline__ float ex2(float x) { float y; asm("ex2.approx.ftz.f32 %0, %1;" : "=f"(y) : "f"(x)); return y; }
__device__ __forceinline__ float rcp(float x) { float y; asm("rcp.approx.ftz.f32 %0, %1;" : "=f"(y) : "f"(x)); return y; }
__device__ __forceinline__ float tanh_ap(float x) { float y; asm("tanh.approx.f32 %0, %1;" : "=f"(y) : "f"(x)); return y; }
__device__ __forceinline__ float gelu_t(float x) {
  float u = x * x;
  float y = x * fmaf(u, 0.0356774081f, 0.7978845608f);
  float hx = 0.5f * x;
  return fmaf(hx, tanh_ap(y), hx);
}
__device__ __forceinline__ void mma16816(float* d, const uint32_t* a, uint32_t b0, uint32_t b1) {
  asm volatile("mma.sync.aligned.m16n8k16.row.col.f32.bf16.bf16.f32 {%0,%1,%2,%3}, {%4,%5,%6,%7}, {%8,%9}, {%0,%1,%2,%3};"
               : "+f"(d[0]), "+f"(d[1]), "+f"(d[2]), "+f"(d[3])
               : "r"(a[0]), "r"(a[1]), "r"(a[2]), "r"(a[3]), "r"(b0), "r"(b1));
}
__device__ __forceinline__ uint64_t mkdesc(uint32_t addr, uint32_t lbo, uint32_t sbo, uint32_t swz) {
  return (uint64_t)((addr & 0x3FFFF) >> 4) | ((uint64_t)(lbo >> 4) << 16) | ((uint64_t)(sbo >> 4) << 32) | ((uint64_t)swz << 62);
}
__device__ __forceinline__ void wg_fence() { asm volatile("wgmma.fence.sync.aligned;" ::: "memory"); }
__device__ __forceinline__ void wg_commit() { asm volatile("wgmma.commit_group.sync.aligned;" ::: "memory"); }
template <int N> __device__ __forceinline__ void wg_wait() { asm volatile("wgmma.wait_group.sync.aligned %0;" ::"n"(N) : "memory"); }
template <int N> __device__ __forceinline__ void reg_fence(float* a) {
#pragma unroll
  for (int i = 0; i < N; i++) asm volatile("" : "+f"(a[i])::"memory");
}

#define F4(a, o) "+f"(a[o]), "+f"(a[o + 1]), "+f"(a[o + 2]), "+f"(a[o + 3])
#define F8(a, o) F4(a, o), F4(a, o + 4)
#define F16(a, o) F8(a, o), F8(a, o + 8)
#define F32(a, o) F16(a, o), F16(a, o + 16)

template <int TA, int TB>
__device__ __forceinline__ void wgmma64(float* d, uint64_t da, uint64_t db, int sd) {
  asm volatile("{\n.reg .pred p;\nsetp.ne.b32 p, %34, 0;\n"
               "wgmma.mma_async.sync.aligned.m64n64k16.f32.bf16.bf16 "
               "{%0,%1,%2,%3,%4,%5,%6,%7,%8,%9,%10,%11,%12,%13,%14,%15,%16,%17,%18,%19,%20,%21,%22,%23,%24,%25,%26,%27,%28,%29,%30,%31},"
               " %32, %33, p, 1, 1, %35, %36;\n}\n"
               : F32(d, 0) : "l"(da), "l"(db), "r"(sd), "n"(TA), "n"(TB));
}
template <int TA, int TB>
__device__ __forceinline__ void wgmma88(float* d, uint64_t da, uint64_t db, int sd) {
  asm volatile("{\n.reg .pred p;\nsetp.ne.b32 p, %46, 0;\n"
               "wgmma.mma_async.sync.aligned.m64n88k16.f32.bf16.bf16 "
               "{%0,%1,%2,%3,%4,%5,%6,%7,%8,%9,%10,%11,%12,%13,%14,%15,%16,%17,%18,%19,%20,%21,%22,%23,%24,%25,%26,%27,%28,%29,%30,%31,"
               "%32,%33,%34,%35,%36,%37,%38,%39,%40,%41,%42,%43},"
               " %44, %45, p, 1, 1, %47, %48;\n}\n"
               : F32(d, 0), F8(d, 32), F4(d, 40) : "l"(da), "l"(db), "r"(sd), "n"(TA), "n"(TB));
}
template <int TA, int TB>
__device__ __forceinline__ void wgmma128(float* d, uint64_t da, uint64_t db, int sd) {
  asm volatile("{\n.reg .pred p;\nsetp.ne.b32 p, %66, 0;\n"
               "wgmma.mma_async.sync.aligned.m64n128k16.f32.bf16.bf16 "
               "{%0,%1,%2,%3,%4,%5,%6,%7,%8,%9,%10,%11,%12,%13,%14,%15,%16,%17,%18,%19,%20,%21,%22,%23,%24,%25,%26,%27,%28,%29,%30,%31,"
               "%32,%33,%34,%35,%36,%37,%38,%39,%40,%41,%42,%43,%44,%45,%46,%47,%48,%49,%50,%51,%52,%53,%54,%55,%56,%57,%58,%59,%60,%61,%62,%63},"
               " %64, %65, p, 1, 1, %67, %68;\n}\n"
               : F32(d, 0), F32(d, 32) : "l"(da), "l"(db), "r"(sd), "n"(TA), "n"(TB));
}

__device__ __forceinline__ float qsum(float v) {
  v += __shfl_xor_sync(0xffffffffu, v, 1);
  return v + __shfl_xor_sync(0xffffffffu, v, 2);
}

__device__ __forceinline__ uint32_t hmul2(uint32_t a, uint32_t b) {
  uint32_t r;
  asm("mul.rn.bf16x2 %0, %1, %2;" : "=r"(r) : "r"(a), "r"(b));
  return r;
}
__device__ __forceinline__ uint32_t movtrans(uint32_t a) {
  uint32_t r;
  asm volatile("movmatrix.sync.aligned.m8n8.trans.b16 %0, %1;" : "=r"(r) : "r"(a));
  return r;
}
__device__ __forceinline__ void hedgehog4(const uint32_t* a, const uint32_t* wb, uint32_t* out) {
  float p[32];
#pragma unroll
  for (int i = 0; i < 32; i++) p[i] = 0.f;
#pragma unroll
  for (int h = 0; h < 4; h++) {
    mma16816(p + 8 * h, a + 4 * h, wb[4 * h], wb[4 * h + 1]);
    mma16816(p + 8 * h + 4, a + 4 * h, wb[4 * h + 2], wb[4 * h + 3]);
  }
  float mx[8], mn[8];
#pragma unroll
  for (int i = 0; i < 8; i++) {
    const float* q = p + 8 * (i >> 1) + 2 * (i & 1);
    mx[i] = fmaxf(fmaxf(q[0], q[1]), fmaxf(q[4], q[5]));
    mn[i] = fminf(fminf(q[0], q[1]), fminf(q[4], q[5]));
  }
#pragma unroll
  for (int o = 1; o <= 2; o++)
#pragma unroll
    for (int i = 0; i < 8; i++) {
      mx[i] = fmaxf(mx[i], __shfl_xor_sync(0xffffffffu, mx[i], o));
      mn[i] = fminf(mn[i], __shfl_xor_sync(0xffffffffu, mn[i], o));
    }
  const float L2E = 1.4426950408889634f;
#pragma unroll
  for (int i = 0; i < 8; i++) {
    const float* q = p + 8 * (i >> 1) + 2 * (i & 1);
    uint32_t* o = out + 8 * (i >> 1) + (i & 1);
    const float a0 = -L2E * mx[i], a1 = L2E * mn[i];
    o[0] = pack2(ex2(fmaf(q[0], L2E, a0)), ex2(fmaf(q[1], L2E, a0)));
    o[2] = pack2(ex2(fmaf(q[4], L2E, a0)), ex2(fmaf(q[5], L2E, a0)));
    o[4] = pack2(ex2(fmaf(q[0], -L2E, a1)), ex2(fmaf(q[1], -L2E, a1)));
    o[6] = pack2(ex2(fmaf(q[4], -L2E, a1)), ex2(fmaf(q[5], -L2E, a1)));
  }
#pragma unroll
  for (int i = 0; i < 8; i++) {
    float sm[4] = {0.f, 0.f, 0.f, 0.f};
    mma16816(sm, out + 4 * i, 0x3F803F80u, 0x3F803F80u);
    const float i0 = rcp(sm[0]), i1 = rcp(sm[2]);
    const uint32_t j0 = pack2(i0, i0), j1 = pack2(i1, i1);
    out[4 * i] = hmul2(out[4 * i], j0); out[4 * i + 1] = hmul2(out[4 * i + 1], j1);
    out[4 * i + 2] = hmul2(out[4 * i + 2], j0); out[4 * i + 3] = hmul2(out[4 * i + 3], j1);
  }
}

__device__ __forceinline__ void poll_ge(const unsigned* p, unsigned target) {
#pragma unroll 1
  for (int it = 0; it < (1 << 22); it++)
    if ((int)(ld_rlx(p) - target) >= 0) return;
  g_err = 1;
}

#define PROF(role, idx) do { } while (0)

struct Params {
  const __nv_bfloat16* x;
  const __nv_bfloat16* wqkv;
  const __nv_bfloat16* wphi;
  const __nv_bfloat16* wo;
  const __nv_bfloat16* win;
  const __nv_bfloat16* wsp;
  const __nv_bfloat16* bsp;
  const __nv_bfloat16* wout;
  __nv_bfloat16* out;
};

__device__ __forceinline__ void ll_stats(const uint2* base, unsigned tag, float n, float inv_tot, float& m0, float& r0, float& m1, float& r1) {
  uint4 v0, v1;
#pragma unroll 1
  for (int it = 0;; it++) {
    asm volatile("{\n.reg .b64 t;\nld.relaxed.gpu.global.b64 t, [%2];\nmov.b64 {%0, %1}, t;\n}" : "=r"(v0.x), "=r"(v0.y) : "l"(base) : "memory");
    asm volatile("{\n.reg .b64 t;\nld.relaxed.gpu.global.b64 t, [%2];\nmov.b64 {%0, %1}, t;\n}" : "=r"(v0.z), "=r"(v0.w) : "l"(base + 128) : "memory");
    asm volatile("{\n.reg .b64 t;\nld.relaxed.gpu.global.b64 t, [%2];\nmov.b64 {%0, %1}, t;\n}" : "=r"(v1.x), "=r"(v1.y) : "l"(base + 8) : "memory");
    asm volatile("{\n.reg .b64 t;\nld.relaxed.gpu.global.b64 t, [%2];\nmov.b64 {%0, %1}, t;\n}" : "=r"(v1.z), "=r"(v1.w) : "l"(base + 136) : "memory");
    const unsigned bad = ((v0.y ^ tag) | (v0.w ^ tag) | (v1.y ^ tag) | (v1.w ^ tag)) & 0xFFu;
    if (__all_sync(0xffffffffu, bad == 0)) break;
    if (it > (1 << 20)) __trap();
    __nanosleep(100);
  }
  const float a0 = __uint_as_float(v0.x), a1 = __uint_as_float(v0.z), b0 = __uint_as_float(v1.x), b1 = __uint_as_float(v1.z);
  m0 = qsum(n * (a0 + a1)) * inv_tot;
  m1 = qsum(n * (b0 + b1)) * inv_tot;
  const float d0 = a0 - m0, d1 = a1 - m0, d2 = b0 - m1, d3 = b1 - m1;
  const float q0 = qsum(__uint_as_float(v0.y & 0xFFFFFF00u) + __uint_as_float(v0.w & 0xFFFFFF00u) + n * (d0 * d0 + d1 * d1));
  const float q1 = qsum(__uint_as_float(v1.y & 0xFFFFFF00u) + __uint_as_float(v1.w & 0xFFFFFF00u) + n * (d2 * d2 + d3 * d3));
  r0 = rsqrtf(q0 * inv_tot + 1e-5f);
  r1 = rsqrtf(q1 * inv_tot + 1e-5f);
  m0 *= -r0;
  m1 *= -r1;
}

__device__ __forceinline__ void acc8(float* s, const uint4& v) {
  s[0] += bf_lo(v.x); s[1] += bf_hi(v.x); s[2] += bf_lo(v.y); s[3] += bf_hi(v.y);
  s[4] += bf_lo(v.z); s[5] += bf_hi(v.z); s[6] += bf_lo(v.w); s[7] += bf_hi(v.w);
}

__global__ void __launch_bounds__(NTHREADS, 1)
fused_kernel(const __grid_constant__ CUtensorMap tm_x, const __grid_constant__ CUtensorMap tm_wkv,
             const __grid_constant__ CUtensorMap tm_wq, const __grid_constant__ CUtensorMap tm_wo,
             const __grid_constant__ CUtensorMap tm_wsp, const __grid_constant__ CUtensorMap tm_wout,
             const __grid_constant__ CUtensorMap tm_out, const Params P) {
  extern __shared__ __align__(1024) unsigned char smem[];
  const uint32_t sb = smem_u32(smem);
  const uint32_t bars = sb + SM_BAR;
  const int tid = threadIdx.x, lane = tid & 31;
  const int warp = __shfl_sync(0xffffffffu, tid >> 5, 0);
  const int bb = (blockIdx.x + 120) & 127;
  const int rb = bb >> 3, j = bb & 7;
  const int cta = rb * 8 + j;
  const int foff = (j == 7) ? 608 : 88 * j;
  const bool full88 = j < 6;
#define BAR(i) (bars + 8 * (i))
#define WSP_PF(q) prefetch_l2((const char*)P.wsp + (size_t)(blockIdx.x * 16 + (q) * 4) * 4096, 16384)

  if (warp >= 8) {
    if (warp == 8) {
      if (lane == 0) { prefetch_map(&tm_x); prefetch_map(&tm_wkv); }
      bar_sync(0, 288);
      if (lane == 0) {
        PROF(2, 3);
#pragma unroll 1
        for (int t = 0; t < 3; t++) {
          mbar_expect_tx(BAR(B_F + t), 32768);
          tma2d(sb + SM_A + t * 16384, &tm_x, t * 64, rb * 128, BAR(B_F + t));
          tma3d(sb + SM_B + t * 16384, &tm_wkv, j * 64, t * 64, 1, BAR(B_F + t));
        }
        prefetch_map(&tm_wq); prefetch_map(&tm_wo); prefetch_map(&tm_wsp); prefetch_map(&tm_wout); prefetch_map(&tm_out);
      }
      __syncwarp();
      bar_sync(6, 288);
      if (lane == 0) {
#pragma unroll 1
        for (int t = 3; t < 6; t++) {
          mbar_wait(BAR(B_F + t - 3), 0);
          mbar_expect_tx(BAR(B_F + t), 32768);
          tma2d(sb + SM_A + t * 16384, &tm_x, t * 64, rb * 128, BAR(B_F + t));
          if (t == 4) {
            mbar_expect_tx(BAR(B_FX67), 32768);
            tma2d(sb + SM_A + 6 * 16384, &tm_x, 6 * 64, rb * 128, BAR(B_FX67));
            tma2d(sb + SM_A + 7 * 16384, &tm_x, 7 * 64, rb * 128, BAR(B_FX67));
          }
          tma3d(sb + SM_B + t * 16384, &tm_wkv, j * 64, t * 64, 1, BAR(B_F + t));
        }
        PROF(2, 4);
#pragma unroll 1
        for (int t = 6; t < 12; t++) {
          const int slot = t < 8 ? t - 6 : 4 + (t & 1);
          mbar_wait(BAR(B_EW + (t < 10 ? slot : t - 8)), 0);
          mbar_expect_tx(BAR(B_F + t), 16384);
          if (t < 8) tma3d(sb + SM_B + slot * 16384, &tm_wkv, j * 64, t * 64, 1, BAR(B_F + t));
          else tma2d(sb + SM_B + slot * 16384, &tm_wq, j * 64, (t - 8) * 128, BAR(B_F + t));
          if (t == 11) {
            prefetch_l2((const char*)P.wo + blockIdx.x * 4096, 4096);
            prefetch_l2((const char*)P.win + blockIdx.x * 11008, 11008);
            WSP_PF(0);
          }
        }
        PROF(2, 0);
#pragma unroll 1
        for (int p = 0; p < 2; p++) {
          mbar_wait(p == 0 ? BAR(B_STG) : BAR(B_P1DONE), 0);
          mbar_expect_tx(BAR(B_FWO + p), 32768);
          tma2d(sb + SM_WO + p * 32768, &tm_wo, j * 64, p * 256, BAR(B_FWO + p));
        }
        mbar_wait(BAR(B_RP), 0);
        red_rel(&g_cnt_cs2[j * 32], 1);
        WSP_PF(1);
        poll_ge(&g_cnt_cs2[j * 32], (ld_rlx(&g_epoch[blockIdx.x * 32]) + 1) * 16);
        mbar_wait(BAR(B_FO + 4), 0);
        fence_async_global();
#pragma unroll 1
        for (int t = 0; t < 8; t++) {
          const int s = t < 4 ? t : (t + 1) & 3;
          if (t == 1) mbar_wait(BAR(B_ISS), 0);
          if (t >= 4) mbar_wait(BAR(B_EMPTY + s), 0);
          if (t == 7) mbar_wait(BAR(B_STG + 3), 0);
          mbar_expect_tx(BAR(B_FWIN + (t & 4) + s), 22528);
          bulk_g2s(sb + SM_Z2 + s * 22528, &g_winp[(j * 8 + (t & 4) + s) * 1408], 22528, BAR(B_FWIN + (t & 4) + s));
        }
        PROF(2, 1);
#pragma unroll 1
        for (int t = 0; t < 20; t++) {
          const int s = (t + 1) & 3;
          mbar_wait(BAR(B_EMPTY + s), ((t >> 2) + 1) & 1);
          if (t == 2 || t == 3) mbar_wait(BAR(B_FZ + t - 2), 0);
          if (t < 16) {
            mbar_expect_tx(BAR(B_FULL + s), 32768);
            tma3d(sb + SM_A + s * 32768, &tm_wsp, 0, rb * 128, ((t + 1) & 15) * 2, BAR(B_FULL + s));
            if (PROFILE && t < 5) PROF(2, 24 + t);
          } else {
            mbar_expect_tx(BAR(B_FWOUT + s), 22528);
            tma2d(sb + SM_Z2 + s * 22528, &tm_wout, j * 64, s * 176, BAR(B_FWOUT + s));
          }
        }
        PROF(2, 2);
      }
    } else {
      const unsigned tag = ld_rlx(&g_epoch[blockIdx.x * 32]) + 1;
      float* csacc = &g_cs[tag & 1][j * 384];
      if (warp >= 10) {
        const int part = warp - 10;
        const uint4* src = (const uint4*)(P.wqkv + (size_t)(rb * 32 + (lane >> 3) * 8) * 1536 + 512 + part * 512 + j * 64 + (lane & 7) * 8);
        const uint4* srq = (const uint4*)(P.wqkv + (size_t)(rb * 32 + (lane >> 2) * 4) * 1536 + j * 64 + part * 32 + (lane & 3) * 8);
        uint4 v[12];
#pragma unroll
        for (int r = 0; r < 8; r++) v[r] = __ldg(src + r * 192);
#pragma unroll
        for (int r = 0; r < 4; r++) v[8 + r] = __ldg(srq + r * 192);
        if (part == 0) ((float4*)&g_kvacc[(j * 16 + rb) * 156])[lane] = make_float4(0.f, 0.f, 0.f, 0.f);
        else if (lane < 7) ((float4*)&g_kvacc[(j * 16 + rb) * 156])[32 + lane] = make_float4(0.f, 0.f, 0.f, 0.f);
        else if (lane < 13) ((float4*)&g_cs[(tag & 1) ^ 1][blockIdx.x * 24])[lane - 7] = make_float4(0.f, 0.f, 0.f, 0.f);
        float s[8] = {0.f, 0.f, 0.f, 0.f, 0.f, 0.f, 0.f, 0.f}, q[8] = {0.f, 0.f, 0.f, 0.f, 0.f, 0.f, 0.f, 0.f};
#pragma unroll
        for (int r = 0; r < 8; r++) acc8(s, v[r]);
#pragma unroll
        for (int r = 0; r < 4; r++) acc8(q, v[8 + r]);
        const bool h1 = lane & 16, h2 = lane & 8, h3 = lane & 4;
#pragma unroll
        for (int i = 0; i < 4; i++) {
          s[i] = (h1 ? s[4 + i] : s[i]) + __shfl_xor_sync(0xffffffffu, h1 ? s[i] : s[4 + i], 16);
          q[i] = (h1 ? q[4 + i] : q[i]) + __shfl_xor_sync(0xffffffffu, h1 ? q[i] : q[4 + i], 16);
        }
#pragma unroll
        for (int i = 0; i < 2; i++) {
          s[i] = (h2 ? s[2 + i] : s[i]) + __shfl_xor_sync(0xffffffffu, h2 ? s[i] : s[2 + i], 8);
          q[i] = (h2 ? q[2 + i] : q[i]) + __shfl_xor_sync(0xffffffffu, h2 ? q[i] : q[2 + i], 8);
        }
        q[0] = (h3 ? q[1] : q[0]) + __shfl_xor_sync(0xffffffffu, h3 ? q[0] : q[1], 4);
        red_v2(csacc + part * 64 + (lane & 7) * 8 + (lane >> 3) * 2, s[0], s[1]);
        red_f32(csacc + 128 + part * 32 + (lane & 3) * 8 + (lane >> 2), q[0]);
        __syncwarp();
        if (lane == 0) red_rel(&g_cnt_cs1[j * 32], 1);
      }
      bar_sync(warp == 9 ? 5 : warp - 3, 288);
      if (warp == 9) {
        {
          const int srow = j * 16 + (lane >> 1);
          if (lane < 16) g_xstat[rb * 128 + j * 16 + lane] = make_uint4(0, tag - 1, 0, tag - 1);
          float s1 = 0.f, s2 = 0.f, s3 = 0.f, s4 = 0.f, shift = 0.f;
#pragma unroll 1
          for (int t = 0; t < 8; t++) {
            mbar_wait(t < 6 ? BAR(B_F + t) : BAR(B_FX67), 0);
            const uint32_t base = sb + SM_A + t * 16384 + srow * 128;
            uint4 v[4];
#pragma unroll
            for (int i = 0; i < 4; i++) v[i] = lds128(base + ((((lane & 1) * 4 + i) ^ (srow & 7)) << 4));
            if (t == 0) shift = __shfl_sync(0xffffffffu, bf_lo(v[0].x), lane & 30);
#pragma unroll
            for (int i = 0; i < 4; i++) {
              float a, b;
              a = bf_lo(v[i].x) - shift; b = bf_hi(v[i].x) - shift; s1 += a; s2 = fmaf(a, a, s2); s3 += b; s4 = fmaf(b, b, s4);
              a = bf_lo(v[i].y) - shift; b = bf_hi(v[i].y) - shift; s1 += a; s2 = fmaf(a, a, s2); s3 += b; s4 = fmaf(b, b, s4);
              a = bf_lo(v[i].z) - shift; b = bf_hi(v[i].z) - shift; s1 += a; s2 = fmaf(a, a, s2); s3 += b; s4 = fmaf(b, b, s4);
              a = bf_lo(v[i].w) - shift; b = bf_hi(v[i].w) - shift; s1 += a; s2 = fmaf(a, a, s2); s3 += b; s4 = fmaf(b, b, s4);
            }
          }
          s1 += s3; s2 += s4;
          s1 += __shfl_xor_sync(0xffffffffu, s1, 1);
          s2 += __shfl_xor_sync(0xffffffffu, s2, 1);
          const float md = s1 * (1.f / 512.f);
          const float rstd = rsqrtf(fmaxf(s2 * (1.f / 512.f) - md * md, 0.f) + 1e-5f);
          if ((lane & 1) == 0) st_ll(&g_xstat[rb * 128 + srow], -(shift + md) * rstd, rstd, tag);
          if (lane == 0) PROF(3, 13);
          uint4 v[4];
#pragma unroll 1
          for (int it = 0;; it++) {
            unsigned bad = 0;
#pragma unroll
            for (int q = 0; q < 4; q++) { v[q] = ld_ll(&g_xstat[rb * 128 + q * 32 + lane]); bad |= (v[q].y ^ tag) | (v[q].w ^ tag); }
            if (__all_sync(0xffffffffu, bad == 0)) break;
            if (it > (1 << 20)) __trap();
          }
#pragma unroll
          for (int q = 0; q < 4; q++) sts64f(sb + SM_XS + (q * 32 + lane) * 8, __uint_as_float(v[q].x), __uint_as_float(v[q].z));
          __syncwarp();
          if (lane == 0) { mbar_arrive(BAR(B_CS1)); PROF(3, 15); }
        }
      } else if (warp == 10) {
        poll_ge(&g_cnt_cs1[j * 32], tag * 32);
        *(float4*)(smem + SM_CS1 + lane * 16) = ld_cg4(csacc + lane * 4);
        if (lane < 16) *(float4*)(smem + SM_CS1 + 512 + lane * 16) = ld_cg4(csacc + 128 + lane * 4);
        __syncwarp();
        if (lane == 0) { mbar_arrive(BAR(B_CS1)); PROF(3, 4); }
      } else {
        mbar_wait(BAR(B_CS1), 0);
#pragma unroll 1
        for (int b = 0; b < 3; b++) {
          uint32_t* base = b == 0 ? g_obuf + (rb * 8 + j) * 4096 : (b == 1 ? g_hbuf + (rb * 8 + j) * 4096 : g_ubuf + (rb * 86 + (foff >> 3)) * 512);
          const int lines = b < 2 ? 128 : (full88 ? 176 : 160);
#pragma unroll 1
          for (int i = lane >> 1; i < lines; i += 16)
            *(uint4*)(base + i * 32 + (i & 24) + (lane & 1) * 4) = make_uint4(0xFFFFFFFFu, 0xFFFFFFFFu, 0xFFFFFFFFu, 0xFFFFFFFFu);
        }
        {
          const uint4 inv = make_uint4(0, tag - 1, 0, tag - 1);
          uint4* zs = (uint4*)&g_zstat[cta * 128];
          uint4* hs = (uint4*)&g_hstat[cta * 128];
          zs[lane] = inv; zs[32 + lane] = inv; hs[lane] = inv; hs[32 + lane] = inv;
        }
        __syncwarp();
        if (lane == 0) { mbar_arrive(BAR(B_POIS)); PROF(3, 5); }
      }
      if (warp == 9) {
#pragma unroll 1
        for (int ph = 0; ph < 3; ph++) {
          const int jj = lane & 7;
          uint32_t pre, fbar, dst, bytes;
          const unsigned* flag;
          const uint32_t* src;
          if (ph < 2) {
            pre = ph == 0 ? BAR(B_P1DONE) : BAR(B_STG + 2);
            fbar = BAR(ph == 0 ? B_FO : B_FH);
            dst = sb + SM_A + jj * 16384;
            bytes = 16384;
            flag = (ph == 0 ? g_flag_o : g_flag_h) + rb * 32 + jj;
            src = (ph == 0 ? g_obuf : g_hbuf) + (rb * 8 + jj) * 4096;
          } else {
            unsigned ready = 0;
#pragma unroll 1
            for (int t = 0; t < 16; t++) {
              const int s = (t + 1) & 3;
              if (t < 4) mbar_wait(BAR(B_FWIN + 4 + s), 0);
              mbar_wait(BAR(B_EMPTY + s), ((t >> 2) + 1) & 1);
              int it = 0;
              while (!((ready >> ((t + 1) & 15)) & 1)) {
                ready = __ballot_sync(0xffffffffu, ld_rlx(&g_flag_z[j * 32 + (lane & 15)]) == tag);
                if (++it > (1 << 22)) __trap();
              }
              if (lane == 0) {
                const uint32_t lb = BAR(B_FULL + s);
                if (t < 2) mbar_arrive(BAR(B_FZ + t));
                if (PROFILE && t < 5) PROF(1, 22 + t);
                mbar_expect_tx(lb, 22528);
                bulk_g2s(sb + SM_Z2 + s * 22528, &g_z2n[(j * 256 + ((t + 1) & 15) * 16) * 352], 22528, lb);
                if (t == 4) prefetch_l2((const char*)P.wout + blockIdx.x * 5504, 5504);
              }
              __syncwarp();
            }
            pre = BAR(B_STG + 4);
            fbar = BAR(B_FU);
            dst = 0;
            bytes = jj >= 6 ? 20480 : 22528;
            flag = g_flag_u + rb * 32 + jj;
            src = g_ubuf + (rb * 86 + (jj == 7 ? 76 : 11 * jj)) * 512;
          }
          bool done = lane >= 8 || jj == j, free_ = false, rdy = false;
          int nissued = 0;
          unsigned ordp = 0;
#pragma unroll 1
          for (int it = 0;; it++) {
            if (!done && !free_) free_ = mbar_test(pre, 0);
            if (!done && free_ && !rdy) rdy = ld_rlx(flag) == tag;
            bool go = !done && rdy;
            unsigned gm = __ballot_sync(0xffffffffu, go);
            if (gm) {
              const int k = nissued + __popc(gm & ((1u << lane) - 1));
              if (ph == 2) {
                if (go && k >= 5) go = mbar_test(BAR(B_EU + k - 5), 0);
                const unsigned stop = __ballot_sync(0xffffffffu, !done && rdy && !go);
                if (stop && lane > __ffs(stop) - 1) go = false;
                gm = __ballot_sync(0xffffffffu, go);
                dst = sb + SM_A + (k >= 5 ? k - 5 : k + 1) * U_SLOT;
              }
              ordp |= __reduce_or_sync(0xffffffffu, go ? jj << (4 * k) : 0);
              if (go) {
                sts32(sb + SM_ORD + ph * 4, ordp | ((nissued + __popc(gm)) << 28));
                mbar_expect_tx(fbar + 8 * k, bytes);
                bulk_g2s(dst, src, bytes, fbar + 8 * k);
                done = true;
              }
            }
            nissued += __popc(gm);
            if (__all_sync(0xffffffffu, done)) break;
            if (it > (1 << 22)) __trap();
          }
          if (lane == 0) PROF(3, ph);
          if (ph == 1) {
        {
          uint4 v[16];
#pragma unroll 1
          for (int it = 0;; it++) {
            unsigned bad = 0;
#pragma unroll
            for (int q = 0; q < 16; q++) v[q] = ld_ll((const uint4*)&g_hstat[(rb * 8 + (q & 7)) * 128 + (q >> 3) * 64 + lane * 2]);
#pragma unroll
            for (int q = 0; q < 16; q++) bad |= (v[q].y ^ tag) | (v[q].w ^ tag);
            if (__all_sync(0xffffffffu, (bad & 0xFFu) == 0)) break;
            if (it > (1 << 20)) __trap();
            __nanosleep(200);
          }
#pragma unroll
          for (int q = 0; q < 2; q++) {
            float ma = 0.f, mb = 0.f, qa = 0.f, qb = 0.f;
#pragma unroll
            for (int i = 0; i < 8; i++) { ma += __uint_as_float(v[q * 8 + i].x); mb += __uint_as_float(v[q * 8 + i].z); }
            ma *= 0.125f; mb *= 0.125f;
#pragma unroll
            for (int i = 0; i < 8; i++) {
              const float d0 = __uint_as_float(v[q * 8 + i].x) - ma, d1 = __uint_as_float(v[q * 8 + i].z) - mb;
              qa += __uint_as_float(v[q * 8 + i].y & 0xFFFFFF00u) + 64.f * d0 * d0;
              qb += __uint_as_float(v[q * 8 + i].w & 0xFFFFFF00u) + 64.f * d1 * d1;
            }
            const float ra = rsqrtf(qa * (1.f / 512.f) + 1e-5f), rbb = rsqrtf(qb * (1.f / 512.f) + 1e-5f);
            *(float4*)(smem + SM_HS + (q * 64 + lane * 2) * 8) = make_float4(-ma * ra, ra, -mb * rbb, rbb);
          }
        }
        __syncwarp();
        if (lane == 0) { mbar_arrive(BAR(B_HS)); PROF(3, 14); }
          }
          if (lane == 0 && ph < 2) WSP_PF(2 + ph);
        }
      } else {
        uint32_t rpar = 0;
        if (warp == 10 && lane == 0) fence_async_global();
#pragma unroll 1
        for (int ph = 0; ph < 5; ph++) {
          if (warp == 10 && lane == 0) {
            uint32_t src, bytes;
            uint32_t* dst;
            unsigned* flag;
            if (ph < 3) {
              src = sb + SM_A + j * 16384; bytes = 16384;
              dst = (ph == 1 ? g_obuf : g_hbuf) + (rb * 8 + j) * 4096;
              flag = (ph == 1 ? g_flag_o : g_flag_h) + rb * 32 + j;
            } else if (ph == 3) {
              src = 0; bytes = 0; dst = nullptr;
              flag = g_flag_z + j * 32 + rb;
            } else {
              src = sb + SM_A; bytes = full88 ? 22528 : 20480;
              dst = g_ubuf + (rb * 86 + (foff >> 3)) * 512;
              flag = g_flag_u + rb * 32 + j;
            }
            mbar_wait(BAR(B_STG + ph), 0);
            if (ph == 0) bulk_red_f32(&g_kvacc[j * 78 * 32], sb + SM_KVP, 9984);
            else if (ph != 3) bulk_s2g(dst, src, bytes);
            if (ph == 2) mbar_arrive(BAR(B_ISS));
            bulk_commit_wait();
            if (ph == 0) mbar_wait(BAR(B_POIS), 0);
            if (ph == 0 || ph == 3) asm volatile("fence.acq_rel.gpu;\nfence.proxy.async.global;" ::: "memory");
            if (ph) st_rlx(flag, tag);
            if (ph != 3) mbar_arrive(BAR(B_PUB + ph));
            PROF(3, 7 + ph);
          }
          __syncwarp();
          if (ph == 0 || ph == 3) continue;
          const int gp = ph == 4 ? 2 : ph - 1;
          unsigned vord = 0;
#pragma unroll 1
          for (int k = 11 - warp; k < 7; k += 2) {
            mbar_wait(BAR((gp == 0 ? B_FO : (gp == 1 ? B_FH : B_FU)) + k), 0);
            if ((int)(vord >> 28) <= k) vord = lds32(sb + SM_ORD + gp * 4);
            const int t = (vord >> (4 * k)) & 7;
            const uint32_t cb = sb + SM_A + (gp < 2 ? t * 16384 : (k >= 5 ? k - 5 : k + 1) * U_SLOT);
            const int nl = gp < 2 ? 128 : (t < 6 ? 176 : 160);
#pragma unroll 1
            for (int it = 0;; it++) {
              bool bad = false;
#pragma unroll
              for (int q = 0; q < 6; q++)
                if (q * 32 + lane < nl) bad |= lds32(cb + q * 4096 + lane * 132) == 0xFFFFFFFFu;
              if (!__any_sync(0xffffffffu, bad)) break;
              if (it > (1 << 16)) __trap();
              if (lane == 0) {
                mbar_expect_tx(BAR(B_RETRY + warp - 10), nl * 128);
                bulk_g2s(cb, gp < 2 ? (gp == 0 ? g_obuf : g_hbuf) + (rb * 8 + t) * 4096
                                    : g_ubuf + (rb * 86 + (t == 7 ? 76 : 11 * t)) * 512,
                         nl * 128, BAR(B_RETRY + warp - 10));
              }
              mbar_wait(BAR(B_RETRY + warp - 10), rpar);
              rpar ^= 1;
            }
            if (lane == 0) mbar_arrive(BAR(B_VAL + k));
          }
          if (ph == 1 && warp == 11) {
        poll_ge(&g_cnt_cs2[j * 32], tag * 16);
        *(float4*)(smem + SM_CS2 + lane * 16) = ld_cg4(csacc + 192 + lane * 4);
        if (lane < 12) *(float4*)(smem + SM_CS2 + 512 + lane * 16) = ld_cg4(csacc + 320 + lane * 4);
        __syncwarp();
        if (lane == 0) { mbar_arrive(BAR(B_CS2)); PROF(3, 12); }
          }
        }
      }
    }
  } else {
    const int g = warp >> 2, w = warp & 3;
    const int lg = lane >> 2, lc = lane & 3;
    const bool leader = (tid & 127) == 0;
    const int row0 = rb * 128 + g * 64 + w * 16 + lg;
    const uint64_t dA_sw = mkdesc(sb + SM_A + g * 8192, 16, 1024, 1);
    const uint64_t dA_ns = mkdesc(sb + SM_A + g * 8192, 1024, 128, 0);
    const uint64_t dB_sw = mkdesc(sb + SM_B, 8192, 1024, 1);
    const uint64_t dB_z = mkdesc(sb + SM_Z2, 1408, 128, 0);
#define STAGED(ph) do { fence_async_smem(); bar_sync(1, 256); if (tid == 0) mbar_arrive(BAR(B_STG + (ph))); } while (0)

    if (lane == 0) {
      mbar_init(BAR(B_F + warp), 1);
      asm volatile("fence.mbarrier_init.release.cluster;" ::: "memory");
    }
    __syncwarp();
    asm volatile("bar.arrive 0, 288;" ::: "memory");
    if (lane == 0) {
#pragma unroll 1
      for (int i = B_F + 8 + warp; i < B_COUNT; i += 8)
        mbar_init(BAR(i), i < B_EW ? 1 : (i <= B_CS1 ? 2 : ((i == B_RP || i == B_STG + 3) ? 8 : 1)));
      asm volatile("fence.mbarrier_init.release.cluster;" ::: "memory");
    }
    __syncwarp();
    asm volatile("bar.arrive 6, 288;\nbar.arrive 5, 288;\nbar.arrive 7, 288;\nbar.arrive 8, 288;" ::: "memory");
    bar_sync(1, 256);
    unsigned tag = ld_rlx(&g_epoch[blockIdx.x * 32]);
    uint32_t wphi[16];
    {
      const uint32_t* wp = (const uint32_t*)P.wphi + j * 512 + lg * 8 + lc;
#pragma unroll
      for (int i = 0; i < 16; i++)
        asm volatile("ld.global.nc.u32 %0, [%1];" : "=r"(wphi[i]) : "l"(wp + (i >> 2) * 128 + (i & 1) * 64 + ((i >> 1) & 1) * 4));
    }

    uint32_t ph[32];
    uint4 rp[4];
    float mean0, rstd0, mean1, rstd1;
    {
      float acc[64];
#pragma unroll 1
      for (int t = 0; t < 8; t++) {
        mbar_wait(BAR(B_F + t), 0);
        if (t == 6) mbar_wait(BAR(B_FX67), 0);
        if (PROFILE && tid == 0 && t == 0) PROF(2, 8);
        const uint64_t da = dA_sw + t * 1024, db = dB_sw + (t < 6 ? t : t - 6) * 1024;
        wg_fence();
#pragma unroll
        for (int kk = 0; kk < 4; kk++) wgmma128<0, 1>(acc, da + kk * 2, db + kk * 128, (t | kk) != 0);
        wg_commit();
        if (t == 7) break;
        wg_wait<1>();
        if (leader && (t == 1 || t == 2 || t == 5 || t == 6)) mbar_arrive(BAR(B_EW + t - 1));
      }
      if (tid == 0) PROF(2, 9);
      float accq[32];
#pragma unroll 1
      for (int t = 0; t < 4; t++) {
        mbar_wait(BAR(B_F + 8 + (t >> 1)), 0);
        const uint64_t da = dA_sw + t * 1024, db = dB_sw + 4096 + t * 512;
        wg_fence();
#pragma unroll
        for (int kk = 0; kk < 4; kk++) wgmma64<0, 1>(accq, da + kk * 2, db + kk * 128, (t | kk) != 0);
        wg_commit();
      }
      asm volatile("" : "+r"(tag));
      tag += 1;
#pragma unroll
      for (int i = 0; i < 16; i++) wphi[i] = movtrans(wphi[i]);
      if (leader) PROF(g, 0);
      mbar_wait(BAR(B_CS1), 0);
      {
        const float2 r0 = lds64f(sb + SM_XS + (g * 64 + w * 16 + lg) * 8), r1 = lds64f(sb + SM_XS + (g * 64 + w * 16 + lg + 8) * 8);
        mean0 = r0.x; rstd0 = r0.y; mean1 = r1.x; rstd1 = r1.y;
      }
      wg_wait<0>();
      reg_fence<64>(acc);
      reg_fence<32>(accq);
      if (leader) { mbar_arrive(BAR(B_EW + 2)); mbar_arrive(BAR(B_EW + 3)); }
      bar_sync(1, 256);
      if (leader) PROF(g, 1);
      {
        const uint32_t a = sb + SM_VS + (g * 8 + w * 2) * 1280 + ((lane >> 3) & 1) * 1280 + (lane & 7) * 16;
#pragma unroll
        for (int b = 0; b < 8; b += 2) {
          const float2 cs = lds64f(sb + SM_CS1 + (64 + b * 8 + 2 * lc) * 4), ct = lds64f(sb + SM_CS1 + (72 + b * 8 + 2 * lc) * 4);
          stsm4(a + (lane >> 4) * 128 + (b >> 2) * 640 + (b & 3) * 128,
                pack2(fmaf(rstd0, acc[32 + 4 * b], mean0 * cs.x), fmaf(rstd0, acc[32 + 4 * b + 1], mean0 * cs.y)),
                pack2(fmaf(rstd1, acc[32 + 4 * b + 2], mean1 * cs.x), fmaf(rstd1, acc[32 + 4 * b + 3], mean1 * cs.y)),
                pack2(fmaf(rstd0, acc[36 + 4 * b], mean0 * ct.x), fmaf(rstd0, acc[36 + 4 * b + 1], mean0 * ct.y)),
                pack2(fmaf(rstd1, acc[36 + 4 * b + 2], mean1 * ct.x), fmaf(rstd1, acc[36 + 4 * b + 3], mean1 * ct.y)));
        }
        stsm4(a + (lane >> 4) * 640 + 512, 0x3F803F80u, 0x3F803F80u, 0x3F803F80u, 0x3F803F80u);
      }
      float src[32];
#pragma unroll
      for (int i = 0; i < 32; i++) src[i] = acc[i];
#pragma unroll 1
      for (int pass = 0; pass < 2; pass++) {
        {
          uint32_t fr[16];
#pragma unroll
          for (int b = 0; b < 8; b++) {
            const float2 cs = lds64f(sb + SM_CS1 + pass * 512 + (b * 8 + 2 * lc) * 4);
            fr[2 * b] = pack2(fmaf(rstd0, src[4 * b], mean0 * cs.x), fmaf(rstd0, src[4 * b + 1], mean0 * cs.y));
            fr[2 * b + 1] = pack2(fmaf(rstd1, src[4 * b + 2], mean1 * cs.x), fmaf(rstd1, src[4 * b + 3], mean1 * cs.y));
          }
          hedgehog4(fr, wphi, ph);
        }
        if (pass == 1) break;
        {
          const uint32_t a = sb + SM_PHIK + (g * 8 + w * 2 + ((lane >> 3) & 1)) * 2048 + (lane >> 4) * 128 + (lane & 7) * 16;
#pragma unroll
          for (int f = 0; f < 16; f += 2) stsm4(a + f * 128, ph[2 * f], ph[2 * f + 1], ph[2 * f + 2], ph[2 * f + 3]);
        }
        fence_async_smem();
        bar_sync(1, 256);
        if (leader) PROF(g, 2);
        {
          const uint64_t da = mkdesc(sb + SM_VS + g * 640, 1280, 128, 0), db = mkdesc(sb + SM_PHIK + g * 1024, 2048, 128, 0);
          wg_fence();
#pragma unroll
          for (int kk = 0; kk < 8; kk++) wgmma64<1, 1>(src, da + kk * 160, db + kk * 256, kk != 0);
          wg_commit();
        }
        wg_wait<0>();
        reg_fence<32>(src);
        {
#define KVADDR(q) (sb + SM_KVP + (q) * 16 + (((q) * 9363) >> 16) * 16 + (lc & 1) * 8)
          if (w < 2) {
            const int q0 = ((g * 2 + w) * 17 + lg) * 8 + (lc >> 1);
#pragma unroll
            for (int b = 0; b < 4; b++) {
              sts64f(KVADDR(q0 + b * 2), w ? src[16 + 4 * b] : src[4 * b], w ? src[16 + 4 * b + 1] : src[4 * b + 1]);
              sts64f(KVADDR(q0 + 64 + b * 2), w ? src[16 + 4 * b + 2] : src[4 * b + 2], w ? src[16 + 4 * b + 3] : src[4 * b + 3]);
            }
          } else if (w == 2) {
            if (lg == 0) {
#pragma unroll
              for (int b = 0; b < 8; b++) sts64f(KVADDR(((g * 2 + (b >> 2)) * 17 + 16) * 8 + (b & 3) * 2 + (lc >> 1)), src[4 * b], src[4 * b + 1]);
            }
          } else {
            const int l = g * 32 + lane;
            *(float4*)(smem + SM_KVP + l * 128 + 112) = make_float4(1.f, 0.f, 0.f, 0.f);
            if (l < 14) *(float4*)(smem + SM_KVP + (64 + l) * 128 + 112) = make_float4(1.f, 0.f, 0.f, 0.f);
            if (l >= 62) *(float4*)(smem + SM_KVP + 77 * 128 + (l - 57) * 16) = make_float4(0.f, 0.f, 0.f, 0.f);
          }
        }
        STAGED(0);
        if (leader) PROF(g, 3);
#pragma unroll
        for (int i = 0; i < 32; i++) src[i] = accq[i];
#pragma unroll 1
        for (int t = 4; t < 8; t++) {
          mbar_wait(BAR(B_F + 8 + (t >> 1)), 0);
          const uint64_t da = dA_sw + t * 1024, db = dB_sw + 2048 + t * 512;
          wg_fence();
#pragma unroll
          for (int kk = 0; kk < 4; kk++) wgmma64<0, 1>(src, da + kk * 2, db + kk * 128, 1);
          wg_commit();
        }
        wg_wait<0>();
        reg_fence<32>(src);
        if (leader) mbar_arrive(BAR(B_P1DONE));
        if (leader) PROF(g, 21);
      }
    }
    const uint32_t own = sb + SM_A + (j * 2 + g) * 8192 + (w * 2 + ((lane >> 3) & 1)) * 128 + (lane >> 4) * 1024 + (lane & 7) * 16;
#define ACQUIRE(gp) do { \
      if ((int)(ordp >> 28) < i) { mbar_wait(BAR(B_VAL + i - 1), (gp) & 1); ordp = lds32(sb + SM_ORD + (gp) * 4); } \
      t = (ordp >> (4 * i - 4)) & 7; } while (0); \
      t = __reduce_or_sync(0xffffffffu, t)
#define ACQWAIT(gp, d0, d1) do { asm volatile("" :: "l"(d0), "l"(d1)); if (i) mbar_wait(BAR(B_VAL + i - 1), (gp) & 1); } while (0)
    if (leader) PROF(g, 4);
    uint32_t hreg[16];
    {
      const uint32_t xa = sb + SM_A + j * 16384 + (g * 64 + w * 16 + (lane & 15)) * 128;
#pragma unroll
      for (int b = 0; b < 8; b += 2) ldsm4(&hreg[2 * b], xa + (((b + (lane >> 4)) ^ (lane & 7)) << 4));
    }
      {
        const int slot = warp * 4 + lc, part = slot >= 12, cid = part ? slot - 12 : slot;
        const uint4* src = (const uint4*)(P.win + (size_t)(rb * 32 + lg) * 1376 + (part ? 0 : 688) + foff + cid * 8);
#pragma unroll
        for (int r = 0; r < 4; r++) {
          rp[r] = make_uint4(0, 0, 0, 0);
          if (warp < 6 && cid < (full88 ? 11 : 10))
            asm volatile("ld.global.nc.v4.u32 {%0,%1,%2,%3}, [%4];" : "=r"(rp[r].x), "=r"(rp[r].y), "=r"(rp[r].z), "=r"(rp[r].w) : "l"(src + r * (8 * 172)));
        }
      }
    {
      const float* src = &g_kvacc[j * 78 * 32];
      float4 v[3];
#pragma unroll 1
      for (int it = 0;; it++) {
        bool bad = false;
#pragma unroll
        for (int i = 0; i < 3; i++)
          if (i < 2 || tid < 112) { v[i] = ld_cg4(src + (tid + i * 256) * 4); bad |= v[i].x != 16.f; }
        if (!__any_sync(0xffffffffu, bad && (lane & 7) == 7)) break;
        if (it > (1 << 18)) __trap();
        __nanosleep(100);
      }
#pragma unroll
      for (int i = 0; i < 3; i++) {
        const int q = (i * 32 + (tid >> 3)) * 7 + (lane & 7);
        if ((lane & 7) != 7 && q < 544)
          *(uint2*)(smem + SM_KVS + (q >> 3) * 80 + (q & 7) * 8) = make_uint2(pack2(v[i].x, v[i].y), pack2(v[i].z, v[i].w));
      }
      bar_sync(1, 256);
    }
    if (leader) PROF(g, 5);
    {
#pragma unroll
      for (int hh = 0; hh < 4; hh++) {
        uint32_t b0[4], b1[4], bz[4];
        const uint32_t kb = sb + SM_KVS + hh * 17 * 80 + (lane >> 3) * 16;
        ldsm4(b0, kb + (lane & 7) * 80);
        ldsm4(b1, kb + (8 + (lane & 7)) * 80);
        ldsm4(bz, kb + 16 * 80);
        float n0[4] = {0.f, 0.f, 0.f, 0.f}, n1[4] = {0.f, 0.f, 0.f, 0.f}, dz[4] = {0.f, 0.f, 0.f, 0.f};
        mma16816(n0, &ph[8 * hh], b0[0], b0[1]); mma16816(n0, &ph[8 * hh + 4], b0[2], b0[3]);
        mma16816(n1, &ph[8 * hh], b1[0], b1[1]); mma16816(n1, &ph[8 * hh + 4], b1[2], b1[3]);
        mma16816(dz, &ph[8 * hh], bz[0], bz[1]); mma16816(dz, &ph[8 * hh + 4], bz[2], bz[3]);
        const float i0 = rcp(dz[0] + 1e-6f), i1 = rcp(dz[2] + 1e-6f);
        stsm4(own + hh * 2048, pack2(n0[0] * i0, n0[1] * i0), pack2(n0[2] * i1, n0[3] * i1), pack2(n1[0] * i0, n1[1] * i0), pack2(n1[2] * i1, n1[3] * i1));
      }
      STAGED(1);
    }
    if (leader) PROF(g, 6);
    {
      const int slot = warp * 4 + lc, part = slot >= 12, cid = part ? slot - 12 : slot;
      const bool live = warp < 6 && cid < 11;
      float q[8] = {0.f, 0.f, 0.f, 0.f, 0.f, 0.f, 0.f, 0.f};
#pragma unroll
      for (int r = 0; r < 4; r++) acc8(q, rp[r]);
      const bool h1 = lane & 16, h2 = lane & 8, h3 = lane & 4;
#pragma unroll
      for (int i = 0; i < 4; i++) q[i] = (h1 ? q[4 + i] : q[i]) + __shfl_xor_sync(0xffffffffu, h1 ? q[i] : q[4 + i], 16);
#pragma unroll
      for (int i = 0; i < 2; i++) q[i] = (h2 ? q[2 + i] : q[i]) + __shfl_xor_sync(0xffffffffu, h2 ? q[i] : q[2 + i], 8);
      q[0] = (h3 ? q[1] : q[0]) + __shfl_xor_sync(0xffffffffu, h3 ? q[0] : q[1], 4);
      mbar_wait(BAR(B_PUB + 1), 0);
      if (live) {
        uint4* dstp = &g_winp[((j * 2 + part) * 64 + rb * 4) * 88 + cid * 8 + lg];
#pragma unroll
        for (int r = 0; r < 4; r++) dstp[r * 88] = rp[r];
        red_f32(&g_cs[tag & 1][j * 384 + 192 + part * 88 + cid * 8 + lg], q[0]);
      }
      __syncwarp();
      if (lane == 0) mbar_arrive(BAR(B_RP));
    }
    {
      float acc[32];
      unsigned ordp = 0;
#pragma unroll 1
      for (int i = 0; i < 8; i++) {
        int t = j;
        if (i == 0) { mbar_wait(BAR(B_FWO), 0); mbar_wait(BAR(B_FWO + 1), 0); }
        else ACQUIRE(0);
        if (PROFILE && tid == 0 && i == 1) PROF(2, 17);
        const uint64_t da = dA_ns + t * 1024, db = dB_sw + 2048 + t * 512;
        ACQWAIT(0, da, db);
        wg_fence();
#pragma unroll
        for (int kk = 0; kk < 4; kk++) wgmma64<0, 1>(acc, da + kk * 128, db + kk * 128, (i | kk) != 0);
        wg_commit();
      }
      mbar_wait(BAR(B_PUB + 1), 0);
      wg_wait<0>();
      reg_fence<32>(acc);
      if (leader) PROF(g, 7);
      float sa = 0.f, sbb = 0.f;
#pragma unroll
      for (int b = 0; b < 8; b++) {
        hreg[2 * b] = pack2(bf_lo(hreg[2 * b]) + acc[4 * b], bf_hi(hreg[2 * b]) + acc[4 * b + 1]);
        hreg[2 * b + 1] = pack2(bf_lo(hreg[2 * b + 1]) + acc[4 * b + 2], bf_hi(hreg[2 * b + 1]) + acc[4 * b + 3]);
        if (b & 1) stsm4(own + (b - 1) * 1024, hreg[2 * b - 2], hreg[2 * b - 1], hreg[2 * b], hreg[2 * b + 1]);
      }
      STAGED(2);
#pragma unroll
      for (int b = 0; b < 8; b++) {
        acc[4 * b] = bf_lo(hreg[2 * b]); acc[4 * b + 1] = bf_hi(hreg[2 * b]);
        acc[4 * b + 2] = bf_lo(hreg[2 * b + 1]); acc[4 * b + 3] = bf_hi(hreg[2 * b + 1]);
        sa += acc[4 * b] + acc[4 * b + 1];
        sbb += acc[4 * b + 2] + acc[4 * b + 3];
      }
      const float ma = qsum(sa) * (1.f / 64.f), mb = qsum(sbb) * (1.f / 64.f);
      float qa = 0.f, qb = 0.f;
#pragma unroll
      for (int b = 0; b < 8; b++) {
        float d;
        d = acc[4 * b] - ma; qa = fmaf(d, d, qa);
        d = acc[4 * b + 1] - ma; qa = fmaf(d, d, qa);
        d = acc[4 * b + 2] - mb; qb = fmaf(d, d, qb);
        d = acc[4 * b + 3] - mb; qb = fmaf(d, d, qb);
      }
      qa = qsum(qa); qb = qsum(qb);
      if (lc < 2) st_ll8(&g_hstat[cta * 128 + (row0 & 127) + lc * 8], lc ? mb : ma, lc ? qb : qa, tag);
    }
    if (leader) PROF(g, 8);
    const float bs0 = __bfloat162float(P.bsp[row0]), bs1 = __bfloat162float(P.bsp[row0 + 8]);
    uint32_t zz[22];
    {
      float acc2[44];
      unsigned ordp = 0;
#pragma unroll 1
      for (int i = 0; i < 8; i++) {
        int t = j;
        if (i == 0) { mbar_wait(BAR(B_FWIN), 0); mbar_wait(BAR(B_FWIN + 1), 0); mbar_wait(BAR(B_FWIN + 2), 0); mbar_wait(BAR(B_FWIN + 3), 0); }
        else ACQUIRE(1);
        if (PROFILE && tid == 0 && i < 2) PROF(2, 18 + i);
        const uint64_t da = dA_ns + t * 1024, db = dB_z + t * 704;
        ACQWAIT(1, da, db);
        wg_fence();
#pragma unroll
        for (int kk = 0; kk < 4; kk++) wgmma88<0, 1>(acc2, da + kk * 128, db + kk * 176, (i | kk) != 0);
        wg_commit();
      }
      if (leader) PROF(g, 9);
      mbar_wait(BAR(B_HS), 0);
      mbar_wait(BAR(B_CS2), 0);
      {
        const float2 r0 = lds64f(sb + SM_HS + (g * 64 + w * 16 + lg) * 8), r1 = lds64f(sb + SM_HS + (g * 64 + w * 16 + lg + 8) * 8);
        mean0 = r0.x; rstd0 = r0.y; mean1 = r1.x; rstd1 = r1.y;
      }
      wg_wait<0>();
      reg_fence<44>(acc2);
      if (leader) { mbar_arrive(BAR(B_EMPTY)); mbar_arrive(BAR(B_EMPTY + 1)); mbar_arrive(BAR(B_EMPTY + 2)); mbar_arrive(BAR(B_EMPTY + 3)); }
      if (leader) PROF(g, 10);
#pragma unroll 1
      for (int pass = 0; pass < 2; pass++) {
        float sa = 0.f, sbb = 0.f, qa = 0.f, qb = 0.f;
#pragma unroll
        for (int b = 0; b < 11; b++) {
          const float2 cs = lds64f(sb + SM_CS2 + pass * 352 + (b * 8 + 2 * lc) * 4);
          const float e0 = gelu_t(fmaf(rstd0, acc2[4 * b], mean0 * cs.x)), e1 = gelu_t(fmaf(rstd0, acc2[4 * b + 1], mean0 * cs.y));
          const float e2 = gelu_t(fmaf(rstd1, acc2[4 * b + 2], mean1 * cs.x)), e3 = gelu_t(fmaf(rstd1, acc2[4 * b + 3], mean1 * cs.y));
          zz[2 * b] = pack2(e0, e1);
          zz[2 * b + 1] = pack2(e2, e3);
          sa += e0 + e1; sbb += e2 + e3;
          qa = fmaf(e0, e0, fmaf(e1, e1, qa)); qb = fmaf(e2, e2, fmaf(e3, e3, qb));
        }
        if (pass == 1) break;
        {
          const float inv_fw = full88 ? (1.f / 88.f) : (1.f / 80.f);
          const bool odd = lc & 1;
          float s = (odd ? sbb : sa) + __shfl_xor_sync(0xffffffffu, odd ? sa : sbb, 1);
          float q = (odd ? qb : qa) + __shfl_xor_sync(0xffffffffu, odd ? qa : qb, 1);
          s += __shfl_xor_sync(0xffffffffu, s, 2);
          q += __shfl_xor_sync(0xffffffffu, q, 2);
          const float m = s * inv_fw;
          if (lc < 2) st_ll8(&g_zstat[cta * 128 + (row0 & 127) + lc * 8], m, fmaxf(q - s * m, 0.f), tag);
        }
        if (leader) PROF(g, 11);
#pragma unroll 1
        for (int i = 0; i < 8; i++) {
          const int t = (i + 2) & 7;
          mbar_wait(BAR(B_FWIN + 4 + (t >> 1)), 0);
          const uint64_t da = dA_ns + t * 1024, db = dB_z + t * 704;
          wg_fence();
#pragma unroll
          for (int kk = 0; kk < 4; kk++) wgmma88<0, 1>(acc2, da + kk * 128, db + kk * 176, (i | kk) != 0);
          wg_commit();
          if (i == 1)
        {
          float zm0, zr0, zm1, zr1;
          ll_stats(&g_zstat[(rb * 8 + 2 * lc) * 128 + (row0 & 127)], tag, (lc == 3) ? 80.f : 88.f, 1.f / 688.f, zm0, zr0, zm1, zr1);
          if (leader) PROF(g, 12);
          uint32_t* zb = &g_z2n[(j * 256 + rb * 16 + g * 8 + w * 2) * 352 + lane];
#pragma unroll
          for (int b = 0; b < 11; b++) {
            zb[b * 32] = pack2(fmaf(bf_lo(zz[2 * b]), zr0, zm0), fmaf(bf_hi(zz[2 * b]), zr0, zm0));
            zb[352 + b * 32] = pack2(fmaf(bf_lo(zz[2 * b + 1]), zr1, zm1), fmaf(bf_hi(zz[2 * b + 1]), zr1, zm1));
          }
          __syncwarp();
          if (lane == 0) mbar_arrive(BAR(B_STG + 3));
          if (leader) PROF(g, 13);
        }
          wg_wait<1>();
          if (leader && i != 0 && (i & 1) == 0) mbar_arrive(BAR(B_EMPTY + (i >> 1)));
        }
        wg_wait<0>();
        reg_fence<44>(acc2);
        if (leader) mbar_arrive(BAR(B_EMPTY));
        if (leader) PROF(g, 14);
      }
    }
    if (leader) PROF(g, 15);
    {
      float acc[44];
#pragma unroll 1
      for (int t = 0; t < 32; t++) {
        const int s = (t + 2) & 7;
        if ((t & 1) == 0) mbar_wait(BAR(B_FULL + (s >> 1)), (t >> 3) & 1);
        const uint64_t da = dA_sw + s * 1024, db = dB_z + s * 704;
        wg_fence();
#pragma unroll
        for (int kk = 0; kk < 4; kk++) wgmma88<0, 1>(acc, da + kk * 2, db + kk * 176, (t | kk) != 0);
        wg_commit();
        wg_wait<1>();
        if (leader && t != 0 && (t & 1) == 0) mbar_arrive(BAR(B_EMPTY + (((s >> 1) + 3) & 3)));
        if (PROFILE && leader && t == 0) PROF(g, 16);
      }
      wg_wait<0>();
      reg_fence<44>(acc);
      if (leader) mbar_arrive(BAR(B_EMPTY));
      if (leader) PROF(g, 17);
      bar_sync(1, 256);
      const uint32_t ub = sb + SM_A + (g * 8 + w * 2 + ((lane >> 3) & 1)) * 128 + (lane & 7) * 16;
#pragma unroll
      for (int b = 0; b < 11; b++) {
        zz[2 * b] = pack2(bf_lo(zz[2 * b]) * (acc[4 * b] + bs0), bf_hi(zz[2 * b]) * (acc[4 * b + 1] + bs0));
        zz[2 * b + 1] = pack2(bf_lo(zz[2 * b + 1]) * (acc[4 * b + 2] + bs1), bf_hi(zz[2 * b + 1]) * (acc[4 * b + 3] + bs1));
        if (b & 1) stsm4(ub + (b - 1 + (lane >> 4)) * 2048, zz[2 * b - 2], zz[2 * b - 1], zz[2 * b], zz[2 * b + 1]);
      }
      stsm4(ub + ((lane >> 4) ? 6 * U_SLOT : 10 * 2048), zz[20], zz[21], 0, 0);
      STAGED(4);
    }
    if (leader) PROF(g, 18);
    {
      float acc[32];
      const uint64_t dA_u = mkdesc(sb + SM_A + g * 1024, 2048, 128, 0);
      const uint64_t dB_o = mkdesc(sb + SM_Z2, 8192, 1024, 1);
      unsigned ordp = 0;
#pragma unroll 1
      for (int i = 0; i < 8; i++) {
        int t = j;
        const int slot = i >= 6 ? i - 6 : i;
        if (i == 0) { mbar_wait(BAR(B_FWOUT), 0); mbar_wait(BAR(B_FWOUT + 1), 0); mbar_wait(BAR(B_FWOUT + 2), 0); mbar_wait(BAR(B_FWOUT + 3), 0); }
        else ACQUIRE(2);
        if (PROFILE && tid == 0 && i == 1) PROF(3, 17);
        const uint64_t da = dA_u + slot * (U_SLOT / 16), db = dB_o + (t == 7 ? 76 : 11 * t) * 64;
        const uint32_t zl = sb + SM_A + g * 1024 + (t < 6 ? slot * U_SLOT + 20480 : 6 * U_SLOT);
        const uint64_t dz = mkdesc(zl, sb + SM_ZERO + g * 1024 - zl, 128, 0);
        ACQWAIT(2, dz, db + 640);
        wg_fence();
        wgmma64<0, 1>(acc, dz, db + 640, i != 0);
#pragma unroll
        for (int kk = 0; kk < 5; kk++) wgmma64<0, 1>(acc, da + kk * 256, db + kk * 128, 1);
        wg_commit();
        if (i < 3) {
          if (i == 0) { wg_wait<0>(); mbar_wait(BAR(B_PUB + 4), 0); }
          else wg_wait<1>();
          if (leader && i != 1) mbar_arrive(BAR(B_EU + (i >> 1)));
        }
      }
      wg_wait<0>();
      reg_fence<32>(acc);
      if (leader) PROF(g, 19);
      bar_sync(1, 256);
      const uint32_t ob = sb + SM_A + (g * 64 + w * 16 + (lane & 15)) * 128;
#pragma unroll
      for (int b = 0; b < 8; b += 2)
        stsm4(ob + (((b + (lane >> 4)) ^ (lane & 7)) << 4),
              pack2(bf_lo(hreg[2 * b]) + acc[4 * b], bf_hi(hreg[2 * b]) + acc[4 * b + 1]),
              pack2(bf_lo(hreg[2 * b + 1]) + acc[4 * b + 2], bf_hi(hreg[2 * b + 1]) + acc[4 * b + 3]),
              pack2(bf_lo(hreg[2 * b + 2]) + acc[4 * b + 4], bf_hi(hreg[2 * b + 2]) + acc[4 * b + 5]),
              pack2(bf_lo(hreg[2 * b + 3]) + acc[4 * b + 6], bf_hi(hreg[2 * b + 3]) + acc[4 * b + 7]));
      fence_async_smem();
      bar_sync(2 + g, 128);
      if (leader) {
        asm volatile("cp.async.bulk.tensor.2d.global.shared::cta.bulk_group [%0, {%2, %3}], [%1];"
                     ::"l"((uint64_t)&tm_out), "r"(sb + SM_A + g * 8192), "r"(j * 64), "r"(rb * 128 + g * 64) : "memory");
        asm volatile("cp.async.bulk.commit_group;\ncp.async.bulk.wait_group.read 0;" ::: "memory");
      }
    }
    if (leader) PROF(g, 20);
    if (tid == 0) g_epoch[blockIdx.x * 32] = tag;
  }
#undef BAR
}

typedef CUresult (*EncodeFn)(CUtensorMap*, CUtensorMapDataType, cuuint32_t, void*, const cuuint64_t*, const cuuint64_t*,
                             const cuuint32_t*, const cuuint32_t*, CUtensorMapInterleave, CUtensorMapSwizzle,
                             CUtensorMapL2promotion, CUtensorMapFloatOOBfill);

void make_map(EncodeFn fn, CUtensorMap* m, const void* ptr, int rows, int cols, int box_cols, int box_rows, CUtensorMapSwizzle swz) {
  cuuint64_t dims[2] = {(cuuint64_t)cols, (cuuint64_t)rows};
  cuuint64_t strides[1] = {(cuuint64_t)cols * 2};
  cuuint32_t box[2] = {(cuuint32_t)box_cols, (cuuint32_t)box_rows};
  cuuint32_t estr[2] = {1, 1};
  fn(m, CU_TENSOR_MAP_DATA_TYPE_BFLOAT16, 2, const_cast<void*>(ptr), dims, strides, box, estr, CU_TENSOR_MAP_INTERLEAVE_NONE, swz,
     CU_TENSOR_MAP_L2_PROMOTION_L2_256B, CU_TENSOR_MAP_FLOAT_OOB_FILL_NONE);
}

}

extern "C" void kernel_launch(void* const* d_in, const int* in_sizes, int n_in, void* d_out, int out_size) {
  static EncodeFn fn = nullptr;
  static CUtensorMap maps[7];
  static const void* cached[10] = {nullptr};
  if (!fn) {
    void* p = nullptr;
    cudaDriverEntryPointQueryResult st;
    cudaGetDriverEntryPoint("cuTensorMapEncodeTiled", &p, cudaEnableDefault, &st);
    fn = (EncodeFn)p;
    cudaFuncSetAttribute(fused_kernel, cudaFuncAttributeMaxDynamicSharedMemorySize, SM_TOTAL);
  }
  bool same = true;
  for (int i = 0; i < 9; i++) same = same && (cached[i] == d_in[i]);
  same = same && cached[9] == d_out;
  if (!same) {
    make_map(fn, &maps[0], d_in[0], 2048, 512, 64, 128, CU_TENSOR_MAP_SWIZZLE_128B);
    {
      cuuint64_t dims[3] = {512, 512, 3};
      cuuint64_t strides[2] = {3072, 1024};
      cuuint32_t box[3] = {64, 64, 2};
      cuuint32_t estr[3] = {1, 1, 1};
      fn(&maps[1], CU_TENSOR_MAP_DATA_TYPE_BFLOAT16, 3, d_in[1], dims, strides, box, estr, CU_TENSOR_MAP_INTERLEAVE_NONE,
         CU_TENSOR_MAP_SWIZZLE_128B, CU_TENSOR_MAP_L2_PROMOTION_L2_256B, CU_TENSOR_MAP_FLOAT_OOB_FILL_NONE);
    }
    make_map(fn, &maps[3], d_in[1], 512, 1536, 64, 128, CU_TENSOR_MAP_SWIZZLE_128B);
    make_map(fn, &maps[2], d_in[3], 512, 512, 64, 256, CU_TENSOR_MAP_SWIZZLE_128B);
    {
      cuuint64_t dims[3] = {64, 2048, 32};
      cuuint64_t strides[2] = {4096, 128};
      cuuint32_t box[3] = {64, 128, 2};
      cuuint32_t estr[3] = {1, 1, 1};
      fn(&maps[4], CU_TENSOR_MAP_DATA_TYPE_BFLOAT16, 3, d_in[6], dims, strides, box, estr, CU_TENSOR_MAP_INTERLEAVE_NONE,
         CU_TENSOR_MAP_SWIZZLE_128B, CU_TENSOR_MAP_L2_PROMOTION_L2_256B, CU_TENSOR_MAP_FLOAT_OOB_FILL_NONE);
    }
    make_map(fn, &maps[5], d_in[8], 688, 512, 64, 176, CU_TENSOR_MAP_SWIZZLE_128B);
    make_map(fn, &maps[6], d_out, 2048, 512, 64, 64, CU_TENSOR_MAP_SWIZZLE_128B);
    for (int i = 0; i < 9; i++) cached[i] = d_in[i];
    cached[9] = d_out;
  }
  Params P;
  P.x = (const __nv_bfloat16*)d_in[0];
  P.wqkv = (const __nv_bfloat16*)d_in[1];
  P.wphi = (const __nv_bfloat16*)d_in[2];
  P.wo = (const __nv_bfloat16*)d_in[3];
  P.win = (const __nv_bfloat16*)d_in[5];
  P.wsp = (const __nv_bfloat16*)d_in[6];
  P.bsp = (const __nv_bfloat16*)d_in[7];
  P.wout = (const __nv_bfloat16*)d_in[8];
  P.out = (__nv_bfloat16*)d_out;
  fused_kernel<<<NCTA, NTHREADS, SM_TOTAL>>>(maps[0], maps[1], maps[3], maps[2], maps[4], maps[5], maps[6], P);
}
```
